```python
import torch

def _softmax(x, axis=-1):
    return torch.softmax(x, dim=axis)
def _gelu(x):
    return torch.nn.functional.gelu(x, approximate="tanh")
def _silu(x):
    return torch.nn.functional.silu(x)
def _sigmoid(x):
    return torch.sigmoid(x)
def _layernorm(x, axis=-1, eps=1e-5):
    m = x.mean(dim=axis, keepdim=True)
    v = x.var(dim=axis, keepdim=True, unbiased=False)
    return (x - m) / torch.sqrt(v + eps)
def _scatter_add(tgt, idx, src, axis=0):
    return tgt.clone().index_add_(axis, idx, src)
def _segment_sum(src, seg, n):
    out = torch.zeros((n,) + src.shape[1:], dtype=src.dtype)
    return out.index_add_(0, seg, src)
def _pad(x, pw):
    flat = tuple(v for pair in reversed(pw) for v in pair)
    return torch.nn.functional.pad(x, flat)

kernel_name = 'concat_heads__mha_block_cached__gqa_block_cached__near_ridge'

def setup_inputs():

    _w = (lambda a: (lambda t: t.to(torch.bfloat16) if t.is_floating_point() else t)(torch.as_tensor(a)))
    def _A_setup():
        B, Sq, D = 8, 144, 1024
        H, Sk, Dh = 32, 512, 128
        return {
            "x": _w((lambda *s: torch.randn(*s, dtype=torch.bfloat16) * 0.8)(B, Sq, D)),
            "k_cache": _w((lambda *s: torch.randn(*s, dtype=torch.bfloat16) * 0.8)(B, H, Sk, Dh)),
            "v_cache": _w((lambda *s: torch.randn(*s, dtype=torch.bfloat16) * 0.05)(B, H, Sk, Dh)),
            "wq": _w((lambda *s: torch.randn(*s, dtype=torch.bfloat16) * 0.8)(D, H * Dh) * (D ** -0.5)),
            "wo": _w((lambda *s: torch.randn(*s, dtype=torch.bfloat16) * 0.05)(H * Dh, D) * ((H * Dh) ** -0.5)),
        }
    _A_in = _A_setup()

    def _B_setup():
        B, Sq, D = 8, 144, 1024
        Hq, Hkv, Sk, Dh = 32, 32, 512, 128
        assert Hq % Hkv == 0, (Hq, Hkv)
        return {
            "x": _w((lambda *s: torch.randn(*s, dtype=torch.bfloat16) * 0.8)(B, Sq, D)),
            "k_cache": _w((lambda *s: torch.randn(*s, dtype=torch.bfloat16) * 0.8)(B, Hkv, Sk, Dh)),
            "v_cache": _w((lambda *s: torch.randn(*s, dtype=torch.bfloat16) * 0.05)(B, Hkv, Sk, Dh)),
            "wq": _w((lambda *s: torch.randn(*s, dtype=torch.bfloat16) * 0.8)(D, Hq * Dh) * (D ** -0.5)),
            "wo": _w((lambda *s: torch.randn(*s, dtype=torch.bfloat16) * 0.05)(Hq * Dh, D) * ((Hq * Dh) ** -0.5)),
        }
    _B_in = _B_setup()

    return {
        "A_x": _A_in["x"],
        "A_k_cache": _A_in["k_cache"],
        "A_v_cache": _A_in["v_cache"],
        "A_wq": _A_in["wq"],
        "A_wo": _A_in["wo"],
        "B_x": _B_in["x"],
        "B_k_cache": _B_in["k_cache"],
        "B_v_cache": _B_in["v_cache"],
        "B_wq": _B_in["wq"],
        "B_wo": _B_in["wo"],
    }

def reference(A_x, A_k_cache, A_v_cache, A_wq, A_wo, B_x, B_k_cache, B_v_cache, B_wq, B_wo):
    def _A_ref(x, k_cache, v_cache, wq, wo):
        B, Sq, D = x.shape
        H, Dh = 32, 128
        q = (lambda x, *d: x.permute(*d))((x @ wq).reshape(B, Sq, H, Dh), 0, 2, 1, 3)
        scores = torch.einsum("bhqd,bhkd->bhqk", q, k_cache) * (Dh ** -0.5)
        p = _softmax(scores, axis=-1)
        o = torch.einsum("bhqk,bhkd->bhqd", p, v_cache)
        return (lambda x, *d: x.permute(*d))(o, 0, 2, 1, 3).reshape(B, Sq, H * Dh) @ wo

    def _B_ref(x, k_cache, v_cache, wq, wo):
        B, Sq, D = x.shape
        Hq, Dh = 32, 128
        Hkv = k_cache.shape[1]
        rep = Hq // Hkv
        q = (lambda x, *d: x.permute(*d))((x @ wq).reshape(B, Sq, Hq, Dh), 0, 2, 1, 3)
        k = (lambda x, n, axis: torch.repeat_interleave(x, n, dim=axis))(k_cache, rep, axis=1)
        v = (lambda x, n, axis: torch.repeat_interleave(x, n, dim=axis))(v_cache, rep, axis=1)
        scores = torch.einsum("bhqd,bhkd->bhqk", q, k) * (Dh ** -0.5)
        p = _softmax(scores, axis=-1)
        o = torch.einsum("bhqk,bhkd->bhqd", p, v)
        return (lambda x, *d: x.permute(*d))(o, 0, 2, 1, 3).reshape(B, Sq, Hq * Dh) @ wo

    a = _A_ref(A_x, A_k_cache, A_v_cache, A_wq, A_wo)
    b = _B_ref(B_x, B_k_cache, B_v_cache, B_wq, B_wo)
    return torch.concatenate([a, b], axis=-1)
```

```cpp
#include <cuda_runtime.h>
#include <cuda_bf16.h>
#include <cuda.h>
#include <stdint.h>

namespace {

constexpr int SQ = 144;
constexpr int NTHREADS = 384;

constexpr uint32_t PAGE = 18432;
constexpr uint32_t OFF_Q = 131072;
constexpr uint32_t OFF_P = 204800;
constexpr uint32_t OFF_XCH = 225280;
constexpr uint32_t X_MI = 1280, X_AL = 1600;
constexpr uint32_t OFF_DUMMY = OFF_XCH + 2048;
constexpr uint32_t OFF_BAR = OFF_XCH + 3072;
constexpr uint32_t OFF_PROG = OFF_BAR + 304;
constexpr uint32_t SMEM_USED = OFF_BAR + 320;
constexpr uint32_t SMEM_BYTES = SMEM_USED;

__host__ __device__ constexpr uint32_t g_x_off(int s) { return s == 0 ? 135168u : s == 1 ? 51200u : s == 2 ? 0u : 169984u; }
__host__ __device__ constexpr uint32_t g_w0_off(int s) { return s == 0 ? 102400u : s == 1 ? 69632u : s == 2 ? 18432u : 153600u; }
__host__ __device__ constexpr uint32_t g_w1_off(int s) { return s == 0 ? 118784u : s == 1 ? 86016u : s == 2 ? 34816u : 188416u; }
__device__ __forceinline__ int kv_row(int h0, int j) { return (h0 + ((j >> 3) & 1) + (j >> 4) * 8) * 512 + (j & 7) * 64; }
#define NZS 12
#define LAST8 0x75642031u
__device__ __forceinline__ int op_head(int n) { return n < 24 ? (n & ~7) + (n & 3) * 2 + ((n >> 2) & 1) : 24 + ((LAST8 >> (4 * (n - 24))) & 7); }
#define GUNR 1
constexpr int kGUnroll = GUNR;
constexpr int T_N = 1, T_T = 0;
#define ST_ROWS 16
#define PF_LQ 16
#define KV_PACE 400
#define T_PRE 1
#define N_PRE 1
#define POLSTR "createpolicy.fractional.L2::evict_first.b64 %0, 1.0;"
__device__ __forceinline__ uint32_t kv_off(int u) { return 114688u - (uint32_t)(u & 7) * 16384u; }

enum { B_GFULL = 0, B_GEMPTY = 4, B_KVFULL = 8, B_KVEMPTY = 12, B_QFREEA = 16, B_QFREEB = 17, B_QFREEC = 18, B_QREADY = 19, B_OSTG = 21, B_DONE = 25, B_PF = 26, B_PARK = 27, B_PE = 28, B_COUNT = 30 };

struct Maps {
  CUtensorMap x[2], wq[2], k[2], v[2], wo[2], o, os, out;
  CUtensorMap pwq[2];
  const char* kp[2];
  const char* vp[2];
  float smc;
};

__device__ __align__(1024) __nv_bfloat16 g_O[2 * 1152 * 4096];
__device__ unsigned g_oflag[2 * 8 * 32 * 32];
__device__ unsigned g_epoch[128];
__device__ float4 g_part[256 * 18 * 128];
__device__ unsigned g_pflag[256 * 32];
__device__ unsigned g_aflag[64 * 32];

__device__ __forceinline__ uint32_t smem_u32(const void* p) { return (uint32_t)__cvta_generic_to_shared(p); }
__device__ __forceinline__ void mbar_init(uint32_t bar, int cnt) { asm volatile("mbarrier.init.shared::cta.b64 [%0], %1;" ::"r"(bar), "r"(cnt) : "memory"); }
__device__ __forceinline__ void mbar_expect_tx(uint32_t bar, uint32_t bytes) { asm volatile("mbarrier.arrive.expect_tx.shared::cta.b64 _, [%0], %1;" ::"r"(bar), "r"(bytes) : "memory"); }
__device__ __forceinline__ void mbar_arrive(uint32_t bar) { asm volatile("mbarrier.arrive.shared::cta.b64 _, [%0];" ::"r"(bar) : "memory"); }
__device__ __forceinline__ void mbar_arrive_if(uint32_t bar, bool q) {
  asm volatile("{\n.reg .pred p;\nsetp.ne.b32 p, %1, 0;\n@p mbarrier.arrive.shared::cta.b64 _, [%0];\n}\n" ::"r"(bar), "r"((uint32_t)q) : "memory");
}
__device__ __forceinline__ void mbar_arrive_cluster_if(uint32_t bar, uint32_t cta, uint32_t cnt, bool q) {
  asm volatile("{\n.reg .pred p;\n.reg .b32 ra;\nsetp.ne.b32 p, %3, 0;\nmapa.shared::cluster.u32 ra, %0, %1;\n@p mbarrier.arrive.shared::cluster.b64 _, [ra], %2;\n}\n" ::"r"(bar),
               "r"(cta), "r"(cnt), "r"((uint32_t)q) : "memory");
}
__device__ __forceinline__ void mbar_arrive_cluster(uint32_t bar, uint32_t cta, uint32_t cnt) {
  asm volatile("{\n.reg .b32 ra;\nmapa.shared::cluster.u32 ra, %0, %1;\nmbarrier.arrive.shared::cluster.b64 _, [ra], %2;\n}\n" ::"r"(bar), "r"(cta), "r"(cnt) : "memory");
}
__device__ __forceinline__ void mbar_wait(uint32_t bar, uint32_t parity) {
  asm volatile(
      "{\n.reg .pred p;\n"
      "LAB_WAIT:\n"
      "mbarrier.try_wait.parity.shared::cta.b64 p, [%0], %1, 0x989680;\n"
      "@p bra LAB_DONE;\n"
      "bra LAB_WAIT;\n"
      "LAB_DONE:\n}\n" ::"r"(bar), "r"(parity) : "memory");
}
__device__ __forceinline__ bool mbar_try(uint32_t bar, uint32_t parity) {
  uint32_t ok;
  asm volatile("{\n.reg .pred p;\nmbarrier.try_wait.parity.shared::cta.b64 p, [%1], %2, 0x989680;\nselp.b32 %0, 1, 0, p;\n}\n" : "=r"(ok) : "r"(bar), "r"(parity) : "memory");
  return ok != 0;
}
__device__ __forceinline__ unsigned long long gtime() {
  unsigned long long t;
  asm volatile("mov.u64 %0, %globaltimer;" : "=l"(t));
  return t;
}
__device__ __forceinline__ void tma_2d(uint32_t dst, const CUtensorMap* m, int c0, int c1, uint32_t bar) {
  asm volatile("cp.async.bulk.tensor.2d.shared::cluster.global.mbarrier::complete_tx::bytes [%0], [%1, {%3, %4}], [%2];" ::"r"(dst), "l"(m), "r"(bar), "r"(c0), "r"(c1) : "memory");
}
__device__ __forceinline__ void tma_2d_hint(uint32_t dst, const CUtensorMap* m, int c0, int c1, uint32_t bar, uint64_t pol) {
  asm volatile("cp.async.bulk.tensor.2d.shared::cluster.global.mbarrier::complete_tx::bytes.L2::cache_hint [%0], [%1, {%3, %4}], [%2], %5;" ::"r"(dst), "l"(m), "r"(bar), "r"(c0), "r"(c1), "l"(pol) : "memory");
}
__device__ __forceinline__ void tma_3d_hint(uint32_t dst, const CUtensorMap* m, int c0, int c1, int c2, uint32_t bar, uint64_t pol) {
  asm volatile("cp.async.bulk.tensor.3d.shared::cluster.global.mbarrier::complete_tx::bytes.L2::cache_hint [%0], [%1, {%3, %4, %5}], [%2], %6;" ::"r"(dst), "l"(m), "r"(bar), "r"(c0), "r"(c1), "r"(c2), "l"(pol) : "memory");
}
__device__ __forceinline__ void tma_3d_mc(uint32_t dst, const CUtensorMap* m, int c0, int c1, int c2, uint32_t bar, uint16_t mask, uint64_t pol) {
  asm volatile("cp.async.bulk.tensor.3d.shared::cluster.global.mbarrier::complete_tx::bytes.multicast::cluster.L2::cache_hint [%0], [%1, {%3, %4, %5}], [%2], %6, %7;" ::"r"(dst), "l"(m), "r"(bar), "r"(c0), "r"(c1), "r"(c2), "h"(mask), "l"(pol) : "memory");
}
__device__ __forceinline__ void tma_store_2d(const CUtensorMap* m, uint32_t src, int c0, int c1) {
  asm volatile("cp.async.bulk.tensor.2d.global.shared::cta.bulk_group [%0, {%2, %3}], [%1];" ::"l"(m), "r"(src), "r"(c0), "r"(c1) : "memory");
}
__device__ __forceinline__ uint64_t mkdesc(uint32_t a16, uint32_t lbo) {
  uint64_t d;
  asm("mov.b64 %0, {%1, %2};" : "=l"(d) : "r"(a16 + ((lbo >> 4) << 16)), "r"(0x40000040u));
  return d;
}
__device__ __forceinline__ uint32_t pack_bf16(float lo, float hi) {
  uint32_t r;
  asm("cvt.rn.bf16x2.f32 %0, %1, %2;" : "=r"(r) : "f"(hi), "f"(lo));
  return r;
}
__device__ __forceinline__ float ex2(float x) {
  float r;
  asm("ex2.approx.ftz.f32 %0, %1;" : "=f"(r) : "f"(x));
  return r;
}
__device__ __forceinline__ int tid_now() {
  int t;
  asm volatile("mov.u32 %0, %%tid.x;" : "=r"(t));
  return t;
}
__device__ __forceinline__ float rcp(float x) {
  float r;
  asm("rcp.approx.ftz.f32 %0, %1;" : "=f"(r) : "f"(x));
  return r;
}
__device__ __forceinline__ float rcp_checked(float x, float lim) {
  float r;
  asm("{\n.reg .pred p;\nrcp.approx.ftz.f32 %0, %1;\nsetp.le.f32 p, %1, %2;\nselp.f32 %0, %0, 0f7FC00000, p;\n}\n" : "=&f"(r) : "f"(x), "f"(lim));
  return r;
}
__device__ __forceinline__ void stsm4(uint32_t addr, uint32_t a, uint32_t b, uint32_t c, uint32_t d) {
  asm volatile("stmatrix.sync.aligned.m8n8.x4.shared.b16 [%0], {%1,%2,%3,%4};" ::"r"(addr), "r"(a), "r"(b), "r"(c), "r"(d) : "memory");
}
__device__ __forceinline__ void stsm4t(uint32_t addr, uint32_t a, uint32_t b, uint32_t c, uint32_t d) {
  asm volatile("stmatrix.sync.aligned.m8n8.x4.trans.shared.b16 [%0], {%1,%2,%3,%4};" ::"r"(addr), "r"(a), "r"(b), "r"(c), "r"(d) : "memory");
}
__device__ __forceinline__ float lds32(uint32_t addr) {
  float v;
  asm volatile("ld.shared.f32 %0, [%1];" : "=f"(v) : "r"(addr) : "memory");
  return v;
}
__device__ __forceinline__ void sts32(uint32_t addr, float a) { asm volatile("st.shared.f32 [%0], %1;" ::"r"(addr), "f"(a) : "memory"); }
__device__ __forceinline__ void sts_volatile(uint32_t addr, int v) { asm volatile("st.volatile.shared.s32 [%0], %1;" ::"r"(addr), "r"(v) : "memory"); }
__device__ __forceinline__ int lds_volatile(uint32_t addr) {
  int v;
  asm volatile("ld.volatile.shared.s32 %0, [%1];" : "=r"(v) : "r"(addr) : "memory");
  return v;
}
#define WG_FENCE() asm volatile("wgmma.fence.sync.aligned;" ::: "memory")
#define WG_COMMIT() asm volatile("wgmma.commit_group.sync.aligned;" ::: "memory")
#define WG_WAIT(n) asm volatile("wgmma.wait_group.sync.aligned %0;" ::"n"(n) : "memory")
#define FENCE_ASYNC_SMEM() asm volatile("fence.proxy.async.shared::cta;" ::: "memory")
__device__ __forceinline__ void bar_sync(int id, int n) { asm volatile("bar.sync %0, %1;" ::"r"(id), "r"(n) : "memory"); }
__device__ __forceinline__ void bar_arrive(int id, int n) { asm volatile("bar.arrive %0, %1;" ::"r"(id), "r"(n) : "memory"); }
template <int N>
__device__ __forceinline__ void reg_fence(float (&a)[N]) {
#pragma unroll
  for (int i = 0; i < N; i++) asm volatile("" : "+f"(a[i])::"memory");
}
template <int N>
__device__ __forceinline__ void reg_zero(float (&a)[N]) {
#pragma unroll
  for (int i = 0; i < N; i++) asm volatile("mov.b32 %0, 0;" : "=f"(a[i])::"memory");
}

__device__ __forceinline__ void wgmma_ss_n144_ta1_tb0(float (&d)[72], uint64_t da, uint64_t db, int scaleD) {
  asm volatile("{\n.reg .pred p;\nsetp.ne.b32 p, %74, 0;\n"
  "wgmma.mma_async.sync.aligned.m64n144k16.f32.bf16.bf16 "
  "{%0, %1, %2, %3, %4, %5, %6, %7, %8, %9, %10, %11, %12, %13, %14, %15, %16, %17, %18, %19, %20, %21, %22, %23, %24, %25, %26, %27, %28, %29, %30, %31, %32, %33, %34, %35, %36, %37, %38, %39, %40, %41, %42, %43, %44, %45, %46, %47, %48, %49, %50, %51, %52, %53, %54, %55, %56, %57, %58, %59, %60, %61, %62, %63, %64, %65, %66, %67, %68, %69, %70, %71}, %72, %73, p, 1, 1, 1, 0;\n}\n"
  : "+f"(d[0]), "+f"(d[1]), "+f"(d[2]), "+f"(d[3]), "+f"(d[4]), "+f"(d[5]), "+f"(d[6]), "+f"(d[7]), "+f"(d[8]), "+f"(d[9]), "+f"(d[10]), "+f"(d[11]), "+f"(d[12]), "+f"(d[13]), "+f"(d[14]), "+f"(d[15]), "+f"(d[16]), "+f"(d[17]), "+f"(d[18]), "+f"(d[19]), "+f"(d[20]), "+f"(d[21]), "+f"(d[22]), "+f"(d[23]), "+f"(d[24]), "+f"(d[25]), "+f"(d[26]), "+f"(d[27]), "+f"(d[28]), "+f"(d[29]), "+f"(d[30]), "+f"(d[31]), "+f"(d[32]), "+f"(d[33]), "+f"(d[34]), "+f"(d[35]), "+f"(d[36]), "+f"(d[37]), "+f"(d[38]), "+f"(d[39]), "+f"(d[40]), "+f"(d[41]), "+f"(d[42]), "+f"(d[43]), "+f"(d[44]), "+f"(d[45]), "+f"(d[46]), "+f"(d[47]), "+f"(d[48]), "+f"(d[49]), "+f"(d[50]), "+f"(d[51]), "+f"(d[52]), "+f"(d[53]), "+f"(d[54]), "+f"(d[55]), "+f"(d[56]), "+f"(d[57]), "+f"(d[58]), "+f"(d[59]), "+f"(d[60]), "+f"(d[61]), "+f"(d[62]), "+f"(d[63]), "+f"(d[64]), "+f"(d[65]), "+f"(d[66]), "+f"(d[67]), "+f"(d[68]), "+f"(d[69]), "+f"(d[70]), "+f"(d[71])
  : "l"(da), "l"(db), "r"(scaleD));
}
__device__ __forceinline__ void wgmma_rs_n64_ta0_tb0(float (&d)[32], uint32_t a0, uint32_t a1, uint32_t a2, uint32_t a3, uint64_t db, int scaleD) {
  asm volatile("{\n.reg .pred p;\nsetp.ne.b32 p, %37, 0;\n"
  "wgmma.mma_async.sync.aligned.m64n64k16.f32.bf16.bf16 "
  "{%0, %1, %2, %3, %4, %5, %6, %7, %8, %9, %10, %11, %12, %13, %14, %15, %16, %17, %18, %19, %20, %21, %22, %23, %24, %25, %26, %27, %28, %29, %30, %31}, {%32, %33, %34, %35}, %36, p, 1, 1, 0;\n}\n"
  : "+f"(d[0]), "+f"(d[1]), "+f"(d[2]), "+f"(d[3]), "+f"(d[4]), "+f"(d[5]), "+f"(d[6]), "+f"(d[7]), "+f"(d[8]), "+f"(d[9]), "+f"(d[10]), "+f"(d[11]), "+f"(d[12]), "+f"(d[13]), "+f"(d[14]), "+f"(d[15]), "+f"(d[16]), "+f"(d[17]), "+f"(d[18]), "+f"(d[19]), "+f"(d[20]), "+f"(d[21]), "+f"(d[22]), "+f"(d[23]), "+f"(d[24]), "+f"(d[25]), "+f"(d[26]), "+f"(d[27]), "+f"(d[28]), "+f"(d[29]), "+f"(d[30]), "+f"(d[31])
  : "r"(a0), "r"(a1), "r"(a2), "r"(a3), "l"(db), "r"(scaleD));
}
__device__ __forceinline__ void wgmma_rs_n128_ta0_tb1(float (&d)[64], uint32_t a0, uint32_t a1, uint32_t a2, uint32_t a3, uint64_t db, int scaleD) {
  asm volatile("{\n.reg .pred p;\nsetp.ne.b32 p, %69, 0;\n"
  "wgmma.mma_async.sync.aligned.m64n128k16.f32.bf16.bf16 "
  "{%0, %1, %2, %3, %4, %5, %6, %7, %8, %9, %10, %11, %12, %13, %14, %15, %16, %17, %18, %19, %20, %21, %22, %23, %24, %25, %26, %27, %28, %29, %30, %31, %32, %33, %34, %35, %36, %37, %38, %39, %40, %41, %42, %43, %44, %45, %46, %47, %48, %49, %50, %51, %52, %53, %54, %55, %56, %57, %58, %59, %60, %61, %62, %63}, {%64, %65, %66, %67}, %68, p, 1, 1, 1;\n}\n"
  : "+f"(d[0]), "+f"(d[1]), "+f"(d[2]), "+f"(d[3]), "+f"(d[4]), "+f"(d[5]), "+f"(d[6]), "+f"(d[7]), "+f"(d[8]), "+f"(d[9]), "+f"(d[10]), "+f"(d[11]), "+f"(d[12]), "+f"(d[13]), "+f"(d[14]), "+f"(d[15]), "+f"(d[16]), "+f"(d[17]), "+f"(d[18]), "+f"(d[19]), "+f"(d[20]), "+f"(d[21]), "+f"(d[22]), "+f"(d[23]), "+f"(d[24]), "+f"(d[25]), "+f"(d[26]), "+f"(d[27]), "+f"(d[28]), "+f"(d[29]), "+f"(d[30]), "+f"(d[31]), "+f"(d[32]), "+f"(d[33]), "+f"(d[34]), "+f"(d[35]), "+f"(d[36]), "+f"(d[37]), "+f"(d[38]), "+f"(d[39]), "+f"(d[40]), "+f"(d[41]), "+f"(d[42]), "+f"(d[43]), "+f"(d[44]), "+f"(d[45]), "+f"(d[46]), "+f"(d[47]), "+f"(d[48]), "+f"(d[49]), "+f"(d[50]), "+f"(d[51]), "+f"(d[52]), "+f"(d[53]), "+f"(d[54]), "+f"(d[55]), "+f"(d[56]), "+f"(d[57]), "+f"(d[58]), "+f"(d[59]), "+f"(d[60]), "+f"(d[61]), "+f"(d[62]), "+f"(d[63])
  : "r"(a0), "r"(a1), "r"(a2), "r"(a3), "l"(db), "r"(scaleD));
}
__device__ __forceinline__ void wgmma_ss_n80_ta0_tb0(float (&d)[40], uint64_t da, uint64_t db, int scaleD) {
  asm volatile("{\n.reg .pred p;\nsetp.ne.b32 p, %42, 0;\n"
  "wgmma.mma_async.sync.aligned.m64n80k16.f32.bf16.bf16 "
  "{%0, %1, %2, %3, %4, %5, %6, %7, %8, %9, %10, %11, %12, %13, %14, %15, %16, %17, %18, %19, %20, %21, %22, %23, %24, %25, %26, %27, %28, %29, %30, %31, %32, %33, %34, %35, %36, %37, %38, %39}, %40, %41, p, 1, 1, 0, 0;\n}\n"
  : "+f"(d[0]), "+f"(d[1]), "+f"(d[2]), "+f"(d[3]), "+f"(d[4]), "+f"(d[5]), "+f"(d[6]), "+f"(d[7]), "+f"(d[8]), "+f"(d[9]), "+f"(d[10]), "+f"(d[11]), "+f"(d[12]), "+f"(d[13]), "+f"(d[14]), "+f"(d[15]), "+f"(d[16]), "+f"(d[17]), "+f"(d[18]), "+f"(d[19]), "+f"(d[20]), "+f"(d[21]), "+f"(d[22]), "+f"(d[23]), "+f"(d[24]), "+f"(d[25]), "+f"(d[26]), "+f"(d[27]), "+f"(d[28]), "+f"(d[29]), "+f"(d[30]), "+f"(d[31]), "+f"(d[32]), "+f"(d[33]), "+f"(d[34]), "+f"(d[35]), "+f"(d[36]), "+f"(d[37]), "+f"(d[38]), "+f"(d[39])
  : "l"(da), "l"(db), "r"(scaleD));
}
__device__ __forceinline__ void wgmma_ss_n80_ta1_tb0(float (&d)[40], uint64_t da, uint64_t db, int scaleD) {
  asm volatile("{\n.reg .pred p;\nsetp.ne.b32 p, %42, 0;\n"
  "wgmma.mma_async.sync.aligned.m64n80k16.f32.bf16.bf16 "
  "{%0, %1, %2, %3, %4, %5, %6, %7, %8, %9, %10, %11, %12, %13, %14, %15, %16, %17, %18, %19, %20, %21, %22, %23, %24, %25, %26, %27, %28, %29, %30, %31, %32, %33, %34, %35, %36, %37, %38, %39}, %40, %41, p, 1, 1, 1, 0;\n}\n"
  : "+f"(d[0]), "+f"(d[1]), "+f"(d[2]), "+f"(d[3]), "+f"(d[4]), "+f"(d[5]), "+f"(d[6]), "+f"(d[7]), "+f"(d[8]), "+f"(d[9]), "+f"(d[10]), "+f"(d[11]), "+f"(d[12]), "+f"(d[13]), "+f"(d[14]), "+f"(d[15]), "+f"(d[16]), "+f"(d[17]), "+f"(d[18]), "+f"(d[19]), "+f"(d[20]), "+f"(d[21]), "+f"(d[22]), "+f"(d[23]), "+f"(d[24]), "+f"(d[25]), "+f"(d[26]), "+f"(d[27]), "+f"(d[28]), "+f"(d[29]), "+f"(d[30]), "+f"(d[31]), "+f"(d[32]), "+f"(d[33]), "+f"(d[34]), "+f"(d[35]), "+f"(d[36]), "+f"(d[37]), "+f"(d[38]), "+f"(d[39])
  : "l"(da), "l"(db), "r"(scaleD));
}

constexpr float SM_C = 0.08838834764831845f * 1.4426950408889634f;

struct Ctx {
  uint32_t sb;
  static constexpr uint32_t s16 = 64;
  uint32_t bar;
  int wg, warp, lane;
  int lead;
  int vb;
  float smc;
  const char *kg, *vg;
  int h0;
};

__device__ __forceinline__ void pp_sync(int wg) { bar_sync(1 + wg, 256); }
__device__ __forceinline__ void pp_arrive(int wg) { bar_arrive(2 - wg, 256); }

enum { G_QP, G_QPARK, G_OPF };
constexpr uint64_t pack_off(uint32_t a, uint32_t b, uint32_t c, uint32_t d) {
  return (uint64_t)(a / 16 + Ctx::s16) | (uint64_t)(b / 16 + Ctx::s16) << 16 | (uint64_t)(c / 16 + Ctx::s16) << 32 | (uint64_t)(d / 16 + Ctx::s16) << 48;
}
constexpr uint64_t G_X16 = pack_off(g_x_off(0), g_x_off(1), g_x_off(2), g_x_off(3));
constexpr uint64_t G_W016 = pack_off(g_w0_off(0), g_w0_off(1), g_w0_off(2), g_w0_off(3));
constexpr uint64_t G_W116 = pack_off(g_w1_off(0), g_w1_off(1), g_w1_off(2), g_w1_off(3));
__device__ __forceinline__ uint32_t pick16(uint64_t t, int s) { return (uint32_t)(t >> (16 * s)) & 0xffffu; }
template <bool OPF>
__device__ __forceinline__ void gemm_phase(const Ctx& c, int qmode, int nk, uint32_t ph, int kh, unsigned epoch) {
  const int mode = OPF ? G_OPF : qmode;
  float a0[72], a1[72];
  reg_zero(a0);
  reg_zero(a1);
  const int tid = tid_now() & 127;
  const int wg = c.wg;
  const int wv = tid_now() >> 7;
  const bool lead = tid == 0;
  const uint32_t m0 = OPF && kh == 0 ? 512 : 0, m1 = 512 - m0;
  const uint64_t wtab = wg ? G_W116 : G_W016;
#pragma unroll kGUnroll
  for (int k = 0; k < nk; k++) {
    const int s = k & 3;
    if (wg == 0) mbar_wait(c.bar + (B_GFULL + s) * 8, (k >> 2) & 1);
    const uint32_t wa = pick16(wtab, s), xa = pick16(G_X16, s);
    if (OPF || k != nk - 1)
    pp_sync(wv);
    WG_FENCE();
#pragma unroll
    for (int kk = 0; kk < 4; kk++) {
      wgmma_ss_n144_ta1_tb0(a0, mkdesc(wa + m0 + kk * 128, 8192), mkdesc(xa + kk * 2, 16), 1);
      wgmma_ss_n144_ta1_tb0(a1, mkdesc(wa + m1 + kk * 128, 8192), mkdesc(xa + kk * 2, 16), 1);
    }
    WG_COMMIT();
    if (OPF || k != nk - 2)
    pp_arrive(wv);
    WG_WAIT(0);
    mbar_arrive_cluster_if(c.bar + (B_GEMPTY + s) * 8, tid & 1, 2, (tid < 2) & (k < nk - (mode == G_QPARK ? 2 : 4)));
    if (!OPF) mbar_arrive_if(c.bar + (B_QFREEA - 1 + s) * 8, lead & (k > nk - 4) & ((s < 3) | (wv == 0)));
  }
  reg_fence(a0);
  reg_fence(a1);
  if (OPF) {
    const int me = c.vb * 2 + wv;
    uint4* xo = reinterpret_cast<uint4*>(g_part) + (size_t)me * (9 * 128) + tid;
#pragma unroll
    for (int j = 0; j < 9; j++)
      __stcg(xo + j * 128, make_uint4(pack_bf16(a0[8 * j], a0[8 * j + 1]), pack_bf16(a0[8 * j + 2], a0[8 * j + 3]), pack_bf16(a0[8 * j + 4], a0[8 * j + 5]),
                                      pack_bf16(a0[8 * j + 6], a0[8 * j + 7])));
    bar_arrive(8 - wv, 256);
    bar_sync(3 + wv, 128);
    if (lead) {
      __threadfence();
      asm volatile("st.relaxed.gpu.global.u32 [%0], %1;" ::"l"(&g_pflag[me * 32]), "r"(epoch) : "memory");
      unsigned v;
      do {
        asm volatile("ld.acquire.gpu.global.u32 %0, [%1];" : "=r"(v) : "l"(&g_pflag[(me ^ 128) * 32]) : "memory");
      } while (v != epoch);
    }
    bar_sync(3 + wv, 128);
    const uint4* xi = reinterpret_cast<const uint4*>(g_part) + (size_t)(me ^ 128) * (9 * 128) + tid;
#pragma unroll
    for (int j = 0; j < 9; j++) {
      const uint4 v = __ldcg(xi + j * 128);
      a1[8 * j] += __uint_as_float(v.x << 16); a1[8 * j + 1] += __uint_as_float(v.x & 0xffff0000u);
      a1[8 * j + 2] += __uint_as_float(v.y << 16); a1[8 * j + 3] += __uint_as_float(v.y & 0xffff0000u);
      a1[8 * j + 4] += __uint_as_float(v.z << 16); a1[8 * j + 5] += __uint_as_float(v.z & 0xffff0000u);
      a1[8 * j + 6] += __uint_as_float(v.w << 16); a1[8 * j + 7] += __uint_as_float(v.w & 0xffff0000u);
    }
  }
  if (OPF) bar_sync(7 + wv, 256);
  const bool park = mode == G_QPARK;
  if (!OPF && !(park && wg == 0)) mbar_wait(c.bar + (wv ? B_QFREEC : B_QFREEA) * 8, ph);
  const int mi = (tid >> 3) & 3, ri = tid & 7;
  const uint32_t lo = c.sb + ((mi >> 1) * 8 + ri) * 128 + (((2 * (tid >> 5) + (mi & 1)) ^ ri) << 4);
  const uint32_t dst1 = lo + (park && wv == 0 ? OFF_P : OFF_Q + wv * 2 * PAGE + PAGE);
  const uint32_t dst = lo + (park ? (wv ? OFF_P : 0) : OFF_Q + wv * 2 * PAGE);
#pragma unroll
  for (int j = 0; j < 18; j += 2)
    stsm4t(dst1 + j * 1024, pack_bf16(a1[4 * j], a1[4 * j + 1]), pack_bf16(a1[4 * j + 2], a1[4 * j + 3]), pack_bf16(a1[4 * j + 4], a1[4 * j + 5]),
           pack_bf16(a1[4 * j + 6], a1[4 * j + 7]));
  if (!OPF) {
    if (park) {
      FENCE_ASYNC_SMEM();
      __syncwarp();
      mbar_arrive_if(c.bar + (B_PE + wv) * 8, (tid & 31) == 0);
      mbar_wait(c.bar + (wv ? B_PARK : B_QFREEB) * 8, 0);
    }
#pragma unroll
    for (int j = 0; j < 18; j += 2)
      stsm4t(dst + j * 1024, pack_bf16(a0[4 * j], a0[4 * j + 1]), pack_bf16(a0[4 * j + 2], a0[4 * j + 3]), pack_bf16(a0[4 * j + 4], a0[4 * j + 5]),
             pack_bf16(a0[4 * j + 6], a0[4 * j + 7]));
  }
  FENCE_ASYNC_SMEM();
  bar_sync(3 + wv, 128);
  mbar_arrive_if(c.bar + (B_QREADY + wv) * 8, lead);
}

constexpr float SM_LIM = 1.2676506e30f;
__device__ __forceinline__ int k_u(int h) { return h < 2 ? h : 2 * h - 2; }
__device__ __forceinline__ int v_u(int h, int nt) { return h < nt ? 2 * h - 1 : 6 + (h & 1); }
__device__ __forceinline__ void release_step(const Ctx& c, int h, int nt) {
  asm volatile("{\n.reg .pred p;\nsetp.ne.b32 p, %1, 0;\n@p mbarrier.arrive.shared::cta.b64 _, [%0];\n}\n" ::"r"(c.bar + (B_KVEMPTY + ((h > nt ? 3 : h - 1) & 3)) * 8),
               "r"(h == nt ? 0 : c.lead) : "memory");
}
__device__ __forceinline__ bool bar_or(int id, int n, bool q) {
  uint32_t r;
  asm volatile("{\n.reg .pred p, q;\nsetp.ne.b32 q, %3, 0;\nbar.red.or.pred p, %1, %2, q;\nselp.b32 %0, 1, 0, p;\n}\n" : "=r"(r) : "r"(id), "r"(n), "r"((uint32_t)q) : "memory");
  return r != 0;
}
__device__ __forceinline__ void sched_fence(uint32_t& tk) {
  asm volatile("{\n.reg .b32 t;\nmov.u32 t, %%clock;\nxor.b32 %0, %0, t;\n}\n" : "+r"(tk)::"memory");
}
__device__ __forceinline__ void pin_before_wait(const Ctx& c, float v) {
  asm volatile("{\n.reg .pred p;\nsetp.lt.f32 p, %2, 0f00000000;\n@p st.shared.f32 [%0], %1;\n}\n" ::"r"(c.sb + OFF_DUMMY), "f"(v), "f"(c.smc) : "memory");
}
__device__ __forceinline__ void attn_exact_rows(const uint2* kp, const uint2* vp, uint32_t qs, int r0, int r1) {
  const int lane = tid_now() & 31;
#pragma unroll 1
  for (int r = r0; r < r1; r++) {
    const uint32_t adr = qs + (lane >> 4) * PAGE + r * 128 + ((((lane >> 1) & 7) ^ (r & 7)) << 4) + (lane & 1) * 8;
    uint32_t qa, qb;
    asm volatile("ld.shared.v2.u32 {%0,%1}, [%2];" : "=r"(qa), "=r"(qb) : "r"(adr) : "memory");
    const float q0 = __uint_as_float(qa << 16), q1 = __uint_as_float(qa & 0xffff0000u), q2 = __uint_as_float(qb << 16), q3 = __uint_as_float(qb & 0xffff0000u);
    float m = -INFINITY, l = 0.f, a0 = 0.f, a1 = 0.f, a2 = 0.f, a3 = 0.f;
#pragma unroll 1
    for (int k = 0; k < 512; k++) {
      const uint2 kk = __ldg(kp + k * 32), vv = __ldg(vp + k * 32);
      float s = q0 * __uint_as_float(kk.x << 16) + q1 * __uint_as_float(kk.x & 0xffff0000u) + q2 * __uint_as_float(kk.y << 16) + q3 * __uint_as_float(kk.y & 0xffff0000u);
#pragma unroll
      for (int o = 16; o; o >>= 1) s += __shfl_xor_sync(0xffffffffu, s, o);
      s *= SM_C;
      const float n = fmaxf(m, s), al = ex2(m - n), p = ex2(s - n);
      m = n;
      l = l * al + p;
      a0 = a0 * al + p * __uint_as_float(vv.x << 16);
      a1 = a1 * al + p * __uint_as_float(vv.x & 0xffff0000u);
      a2 = a2 * al + p * __uint_as_float(vv.y << 16);
      a3 = a3 * al + p * __uint_as_float(vv.y & 0xffff0000u);
    }
    const float inv = rcp(l);
    asm volatile("st.shared.v2.u32 [%0], {%1,%2};" ::"r"(adr), "r"(pack_bf16(a0 * inv, a1 * inv)), "r"(pack_bf16(a2 * inv, a3 * inv)) : "memory");
  }
}

__device__ __forceinline__ void attn_exact(const Ctx& c, int hd, int r0, int nr) {
  const int tn = tid_now(), lane = tn & 31, warp = (tn >> 5) & 3;
  (void)lane; (void)warp;
  const size_t off = (size_t)kv_row(c.h0, hd * 8) * 32 + lane;
  attn_exact_rows(reinterpret_cast<const uint2*>(c.kg) + off, reinterpret_cast<const uint2*>(c.vg) + off, c.sb + OFF_Q + (hd & 1) * 2 * PAGE, r0 + warp * nr, r0 + warp * nr + nr);
}

template <bool QK, bool PV, int K0 = 0, int K1 = 8>
__device__ __forceinline__ void attn0_burst(const Ctx& c, const uint32_t (&Q)[32], float (&S)[32], const uint32_t (&P)[16], float (&O)[64], int h, int nt) {
  const uint32_t ka = c.s16 + (kv_off(k_u(h)) >> 4), va = c.s16 + (kv_off(v_u(h, nt)) >> 4);
  const int first = (h & 7) == 2;
#pragma unroll
  for (int kk = K0; kk < K1; kk++) {
    if (QK) wgmma_rs_n64_ta0_tb0(S, Q[4 * kk], Q[4 * kk + 1], Q[4 * kk + 2], Q[4 * kk + 3], mkdesc(ka + (kk >> 2) * 512 + (kk & 3) * 2, 16), kk != 0);
    if (PV && (kk & 1))
      wgmma_rs_n128_ta0_tb1(O, P[2 * kk - 2], P[2 * kk - 1], P[2 * kk], P[2 * kk + 1], mkdesc(va + (kk >> 1) * 128, 8192), !(first && kk == 1));
  }
}
struct Row0 { float c0, c1, l0, l1, i0, i1; };
__device__ __forceinline__ void ostg_arrive(const Ctx& c, int hh) {
  const int tn = tid_now(), lane = tn & 31, warp = (tn >> 5) & 3;
  (void)lane; (void)warp;
  FENCE_ASYNC_SMEM();
  __syncwarp();
  mbar_arrive_if(c.bar + (B_OSTG + hh * 2 + (tn >> 7)) * 8, lane == 0);
}
__device__ __forceinline__ void attn0_store(const Ctx& c, float (&O)[64], float i0, float i1, int hd) {
  const int tn = tid_now(), lane = tn & 31, warp = (tn >> 5) & 3;
  (void)lane; (void)warp;
  const int hh = hd & 1;
  float z0 = 0.f, z1 = 0.f;
#pragma unroll
  for (int j = 0; j < 16; j++) {
    O[4 * j] *= i0; O[4 * j + 1] *= i0; O[4 * j + 2] *= i1; O[4 * j + 3] *= i1;
    z0 = fmaf(O[4 * j], O[4 * j + 2], z0);
    z1 = fmaf(O[4 * j + 1], O[4 * j + 3], z1);
  }
  if (__builtin_expect(__any_sync(0xffffffffu, !(fabsf(z0 + z1) <= 3e38f)), 0)) {
    attn_exact(c, hd, 0, 16);
  } else {
    const int mi = lane >> 3, ri = lane & 7;
    const uint32_t row = c.sb + OFF_Q + hh * 2 * PAGE + (16 * warp + (mi & 1) * 8 + ri) * 128;
#pragma unroll
    for (int j = 0; j < 16; j += 2)
      stsm4(row + (j >> 3) * PAGE + ((((j & 7) + (mi >> 1)) ^ ri) << 4), pack_bf16(O[4 * j], O[4 * j + 1]), pack_bf16(O[4 * j + 2], O[4 * j + 3]),
            pack_bf16(O[4 * j + 4], O[4 * j + 5]), pack_bf16(O[4 * j + 6], O[4 * j + 7]));
  }
  ostg_arrive(c, hh);
}
__device__ __forceinline__ void n_ex(int g, float (&S)[32]) {
#pragma unroll
  for (int u = 0; u < 8; u++) { S[8 * g + u] = ex2(S[8 * g + u]); asm volatile("" : "+f"(S[8 * g + u])); }
}
__device__ __forceinline__ void n_use(int g, const float (&S)[32], uint32_t (&P)[16], Row0& r) {
  const float* x = &S[8 * g];
#pragma unroll
  for (int u = 0; u < 4; u++) { P[4 * g + u] = pack_bf16(x[2 * u], x[2 * u + 1]); asm volatile("" : "+r"(P[4 * g + u])); }
  r.l0 += (x[0] + x[1]) + (x[4] + x[5]);
  r.l1 += (x[2] + x[3]) + (x[6] + x[7]);
  asm volatile("" : "+f"(r.l0), "+f"(r.l1));
}
template <bool FIRST, bool ODD>
__device__ __forceinline__ void attn0_step(const Ctx& c, uint32_t (&Q)[32], float (&Sa)[32], uint32_t (&Pa)[16], float (&Sb)[32], uint32_t (&Pb)[16], float (&O)[64],
                                           Row0& r, int h, int nt) {
  uint32_t tk = __float_as_uint(r.c0);
  if (!FIRST) {
#pragma unroll
    for (int j = 0; j < 32; j++) Sb[j] = fmaf(Sb[j], SM_C, (j & 2) ? -r.c1 : -r.c0);
    if (N_PRE) n_ex(0, Sb);
    reg_fence(Sb);
  }
  {
    const int p = min(h, nt - 1);
    mbar_wait(c.bar + (B_KVFULL + (p & 3)) * 8, (p >> 2) & 1);
  }
  if (!FIRST) sched_fence(tk);
  pp_sync(T_N);
  WG_FENCE();
  if (FIRST) {
    attn0_burst<true, false>(c, Q, Sa, Pa, O, h, nt);
    WG_COMMIT();
    pp_arrive(T_N);
  } else {
    attn0_burst<true, true, 0, 2>(c, Q, Sa, Pa, O, h, nt);
    sched_fence(tk);
#pragma unroll
    for (int g = 0; g < 3; g++) {
      WG_FENCE();
      if (g == 0) attn0_burst<true, true, 2, 4>(c, Q, Sa, Pa, O, h, nt);
      if (g == 1) attn0_burst<true, true, 4, 6>(c, Q, Sa, Pa, O, h, nt);
      if (g == 2) {
        attn0_burst<true, true, 6, 8>(c, Q, Sa, Pa, O, h, nt);
        WG_COMMIT();
        pp_arrive(T_N);
      }
      n_ex(g + N_PRE, Sb);
      if (g + N_PRE > 0) n_use(g + N_PRE - 1, Sb, Pb, r);
      sched_fence(tk);
    }
    if (!N_PRE) n_ex(3, Sb);
#pragma unroll
    for (int g = 2 + N_PRE; g < 4; g++) n_use(g, Sb, Pb, r);
    pin_before_wait(c, r.l0 + r.l1 + __uint_as_float(tk));
  }
  WG_WAIT(0);
  reg_fence(Sa);
  if (!FIRST) {
    reg_fence(O);
    release_step(c, h, nt);
  }
}
__device__ __forceinline__ void attn0_boundary(const float (&S0)[32], Row0& r) {
  float l0 = r.l0, l1 = r.l1;
  l0 += __shfl_xor_sync(0xffffffffu, l0, 1);
  l1 += __shfl_xor_sync(0xffffffffu, l1, 1);
  r.c0 = __shfl_sync(0xffffffffu, S0[0], tid_now() & 28) * SM_C;
  r.c1 = __shfl_sync(0xffffffffu, S0[2], tid_now() & 28) * SM_C;
  l0 += __shfl_xor_sync(0xffffffffu, l0, 2);
  l1 += __shfl_xor_sync(0xffffffffu, l1, 2);
  r.i0 = rcp_checked(l0, SM_LIM);
  r.i1 = rcp_checked(l1, SM_LIM);
  r.l0 = 0.f;
  r.l1 = 0.f;
}
__device__ __forceinline__ void attn0_loadq(const Ctx& c, uint32_t (&Q)[32], int hh) {
  const int tn = tid_now(), lane = tn & 31, warp = (tn >> 5) & 3;
  (void)lane; (void)warp;
  const int mi = lane >> 3, ri = lane & 7;
  const uint32_t row = c.sb + OFF_Q + hh * 2 * PAGE + (16 * warp + (mi & 1) * 8 + ri) * 128;
#pragma unroll
  for (int kk = 0; kk < 8; kk++)
    asm volatile("ldmatrix.sync.aligned.m8n8.x4.shared.b16 {%0,%1,%2,%3}, [%4];"
                 : "=r"(Q[4 * kk]), "=r"(Q[4 * kk + 1]), "=r"(Q[4 * kk + 2]), "=r"(Q[4 * kk + 3])
                 : "r"(row + (kk >> 2) * PAGE + ((((kk & 3) * 2 + (mi >> 1)) ^ ri) << 4)) : "memory");
}
__device__ __forceinline__ void attn_wg0(const Ctx& c, int nt, uint32_t ph) {
  float S0[32], S1[32], O[64];
  uint32_t P0[16], P1[16], Q[32];
  Row0 r = {0.f, 0.f, 0.f, 0.f, 0.f, 0.f};
  reg_zero(S0);
  reg_zero(S1);
  reg_zero(O);
  if (T_N) mbar_wait(c.bar + B_QREADY * 8, ph);
  attn0_loadq(c, Q, 0);
#pragma unroll
  for (int j = 0; j < 16; j++) { P0[j] = 0; P1[j] = 0; }
  attn0_step<true, false>(c, Q, S0, P0, S1, P1, O, r, 0, nt);
#pragma unroll 1
  for (int h = 0;; h += 2) {
    if ((h & 7) == 0) attn0_boundary(S0, r);
    attn0_step<false, true>(c, Q, S1, P1, S0, P0, O, r, h + 1, nt);
    if ((h & 7) == 0 && h) {
      attn0_store(c, O, r.i0, r.i1, (h >> 3) - 1);
      if (h == nt) break;
    }
    if ((h & 7) == 6 && h + 2 < nt) {
      mbar_wait(c.bar + (B_QREADY + (((h + 2) >> 3) & 1)) * 8, ph ^ ((h + 2) >> 4));
      attn0_loadq(c, Q, ((h + 2) >> 3) & 1);
    }
    attn0_step<false, false>(c, Q, S0, P0, S1, P1, O, r, h + 2, nt);
  }
}

template <bool QK, bool PV, int K0, int K1>
__device__ __forceinline__ void attn1_burst(const Ctx& c, float (&S)[40], float (&O0)[40], float (&O1)[40], int h, int nt) {
  const uint32_t qa = c.s16 + ((OFF_Q + ((h >> 3) & 1) * 2 * PAGE + 8192) >> 4);
  const uint32_t ka = c.s16 + (kv_off(k_u(h)) >> 4), va = c.s16 + (kv_off(v_u(h, nt)) >> 4);
  const uint32_t pa = c.s16 + (OFF_P >> 4) + (h & 1) * 640;
  const int first = (h & 7) == 2;
#pragma unroll
  for (int kk = K0; kk < K1; kk++) {
    if (QK) wgmma_ss_n80_ta0_tb0(S, mkdesc(ka + (kk >> 2) * 512 + (kk & 3) * 2, 16), mkdesc(qa + (kk >> 2) * (PAGE / 16) + (kk & 3) * 2, 16), kk != 0);
    if (PV) {
      const int sc = !(first && kk < 2);
      if (kk & 1) wgmma_ss_n80_ta1_tb0(O1, mkdesc(va + 512 + (kk >> 1) * 128, 8192), mkdesc(pa + (kk >> 1) * 2, 16), sc);
      else wgmma_ss_n80_ta1_tb0(O0, mkdesc(va + (kk >> 1) * 128, 8192), mkdesc(pa + (kk >> 1) * 2, 16), sc);
    }
  }
}
__device__ __forceinline__ void load20(uint32_t addr, float (&v)[20]) {
#pragma unroll
  for (int i = 0; i < 5; i++)
    asm volatile("ld.shared.v4.f32 {%0,%1,%2,%3}, [%4];" : "=f"(v[4 * i]), "=f"(v[4 * i + 1]), "=f"(v[4 * i + 2]), "=f"(v[4 * i + 3]) : "r"(addr + i * 16) : "memory");
}
__device__ __forceinline__ uint32_t stsm_t_lane_off(const Ctx& c) {
  const int tn = tid_now(), lane = tn & 31, warp = (tn >> 5) & 3;
  (void)lane; (void)warp;
  const int mi = lane >> 3, ri = lane & 7;
  return ((mi >> 1) * 8 + ri) * 128 + (((2 * warp + (mi & 1)) ^ ri) << 4);
}
__device__ __forceinline__ void t_ex(int jj, float (&S)[40]) {
#pragma unroll
  for (int u = 0; u < 8; u++) { S[8 * jj + u] = ex2(S[8 * jj + u]); asm volatile("" : "+f"(S[8 * jj + u])); }
}
__device__ __forceinline__ void t_use(int jj, uint32_t dst, const float (&S)[40], float (&l)[20]) {
  const float* x = &S[8 * jj];
  stsm4t(dst + jj * 2048, pack_bf16(x[0], x[1]), pack_bf16(x[2], x[3]), pack_bf16(x[4], x[5]), pack_bf16(x[6], x[7]));
  l[4 * jj] += x[0] + x[2];
  l[4 * jj + 1] += x[1] + x[3];
  l[4 * jj + 2] += x[4] + x[6];
  l[4 * jj + 3] += x[5] + x[7];
#pragma unroll
  for (int u = 0; u < 4; u++) asm volatile("" : "+f"(l[4 * jj + u]));
}
template <bool QK, bool PV, bool EX>
__device__ __forceinline__ void attn1_step(const Ctx& c, float (&Sa)[40], float (&Sb)[40], float (&O0)[40], float (&O1)[40], const float (&m)[20], float (&l)[20],
                                           uint32_t dst, int h, int nt) {
  uint32_t tk = dst;
  if (EX) {
#pragma unroll
    for (int j = 0; j < 40; j++) Sb[j] = fmaf(Sb[j], SM_C, -m[(j >> 2) * 2 + (j & 1)]);
    if (T_PRE) t_ex(0, Sb);
    reg_fence(Sb);
    sched_fence(tk);
  }
  if (T_T == 0 && !PV) mbar_wait(c.bar + B_KVFULL * 8, 0);
  pp_sync(T_T);
  reg_fence(O0);
  reg_fence(O1);
  reg_fence(Sa);
  WG_FENCE();
  if (EX) {
    attn1_burst<QK, PV, 0, 2>(c, Sa, O0, O1, h, nt);
    sched_fence(tk);
#pragma unroll
    for (int r = 0; r < 3; r++) {
      WG_FENCE();
      if (r == 0) attn1_burst<QK, PV, 2, 4>(c, Sa, O0, O1, h, nt);
      if (r == 1) attn1_burst<QK, PV, 4, 6>(c, Sa, O0, O1, h, nt);
      if (r == 2) {
        attn1_burst<QK, PV, 6, 8>(c, Sa, O0, O1, h, nt);
        WG_COMMIT();
        pp_arrive(T_T);
      }
      t_ex(r + T_PRE, Sb);
      if (r + T_PRE > 0) t_use(r + T_PRE - 1, dst, Sb, l);
      sched_fence(tk);
    }
#pragma unroll
    for (int jj = 3 + T_PRE; jj < 5; jj++) t_ex(jj, Sb);
#pragma unroll
    for (int jj = 2 + T_PRE; jj < 5; jj++) t_use(jj, dst, Sb, l);
    pin_before_wait(c, __uint_as_float(tk));
  } else {
    attn1_burst<QK, PV, 0, 8>(c, Sa, O0, O1, h, nt);
    WG_COMMIT();
    pp_arrive(T_T);
  }
  WG_WAIT(0);
  if (PV) release_step(c, h, nt);
  if (EX) FENCE_ASYNC_SMEM();
  reg_fence(O0);
  reg_fence(O1);
  reg_fence(Sa);
}
__device__ __forceinline__ void attn1_store(const Ctx& c, float (&O0)[40], float (&O1)[40], int hd) {
  const int tn = tid_now(), lane = tn & 31, warp = (tn >> 5) & 3;
  (void)lane; (void)warp;
  const int hh = hd & 1;
  const uint32_t inv = c.sb + OFF_XCH + X_AL + (lane & 3) * 80;
  float z0 = 0.f, z1 = 0.f;
#pragma unroll
  for (int jj = 0; jj < 5; jj++) {
    float a[4];
    asm volatile("ld.shared.v4.f32 {%0,%1,%2,%3}, [%4];" : "=f"(a[0]), "=f"(a[1]), "=f"(a[2]), "=f"(a[3]) : "r"(inv + jj * 16) : "memory");
#pragma unroll
    for (int u = 0; u < 8; u++) {
      O0[8 * jj + u] *= a[(u >> 2) * 2 + (u & 1)];
      O1[8 * jj + u] *= a[(u >> 2) * 2 + (u & 1)];
      if (u & 1) z1 = fmaf(O0[8 * jj + u], O1[8 * jj + u], z1);
      else z0 = fmaf(O0[8 * jj + u], O1[8 * jj + u], z0);
    }
  }
  if (__builtin_expect(bar_or(6, 128, !(fabsf(z0 + z1) <= 3e38f)), 0)) {
    attn_exact(c, hd, 64, 20);
  } else {
    const uint32_t dst = c.sb + OFF_Q + hh * 2 * PAGE + 8192 + stsm_t_lane_off(c);
#pragma unroll
    for (int jj = 0; jj < 5; jj++) {
      stsm4t(dst + jj * 2048, pack_bf16(O0[8 * jj], O0[8 * jj + 1]), pack_bf16(O0[8 * jj + 2], O0[8 * jj + 3]), pack_bf16(O0[8 * jj + 4], O0[8 * jj + 5]),
             pack_bf16(O0[8 * jj + 6], O0[8 * jj + 7]));
      stsm4t(dst + PAGE + jj * 2048, pack_bf16(O1[8 * jj], O1[8 * jj + 1]), pack_bf16(O1[8 * jj + 2], O1[8 * jj + 3]), pack_bf16(O1[8 * jj + 4], O1[8 * jj + 5]),
             pack_bf16(O1[8 * jj + 6], O1[8 * jj + 7]));
    }
  }
  ostg_arrive(c, hh);
}
__device__ __forceinline__ void attn1_boundary(const Ctx& c, const float (&S0)[40], float (&l)[20], float (&m)[20], bool SUM, bool SHIFT) {
  const int tn = tid_now(), lane = tn & 31, warp = (tn >> 5) & 3;
  (void)lane; (void)warp;
  const uint32_t xch = c.sb + OFF_XCH;
  if (SHIFT) {
#pragma unroll
    for (int j = 0; j < 5; j++)
      asm volatile("{\n.reg .pred p;\nsetp.lt.u32 p, %5, 4;\n@p st.shared.v4.f32 [%0], {%1,%2,%3,%4};\n}\n" ::"r"(xch + X_MI + lane * 80 + j * 16), "f"(S0[8 * j]),
                   "f"(S0[8 * j + 1]), "f"(S0[8 * j + 4]), "f"(S0[8 * j + 5]), "r"(tn & 127) : "memory");
  }
  if (SUM) {
    const bool b4 = lane & 16, b3 = lane & 8;
    float r[10], q[5];
#pragma unroll
    for (int i = 0; i < 10; i++) r[i] = (b4 ? l[10 + i] : l[i]) + __shfl_xor_sync(0xffffffffu, b4 ? l[i] : l[10 + i], 16);
#pragma unroll
    for (int i = 0; i < 5; i++) q[i] = (b3 ? r[2 * i + 1] : r[2 * i]) + __shfl_xor_sync(0xffffffffu, b3 ? r[2 * i] : r[2 * i + 1], 8);
    const uint32_t dst = xch + warp * 320 + (lane & 3) * 80 + (b4 ? 40 : 0) + (b3 ? 4 : 0);
#pragma unroll
    for (int i = 0; i < 5; i++) sts32(dst + i * 8, q[i] + __shfl_xor_sync(0xffffffffu, q[i], 4));
  }
  bar_sync(6, 128);
  if (SUM) {
    const uint32_t col = xch + min(tn & 127, 79) * 4;
    sts32(col + X_AL, rcp_checked((lds32(col) + lds32(col + 320)) + (lds32(col + 640) + lds32(col + 960)), SM_LIM));
  }
  if (SHIFT) {
    load20(xch + X_MI + (lane & 3) * 80, m);
#pragma unroll
    for (int j = 0; j < 20; j++) m[j] *= SM_C;
  }
#pragma unroll
  for (int j = 0; j < 20; j++) l[j] = 0.f;
}
__device__ __forceinline__ void attn_wg1(const Ctx& c, int nt, uint32_t ph) {
  float S0[40], S1[40], O0[40], O1[40], l[20], m[20];
  reg_zero(S0); reg_zero(S1); reg_zero(O0); reg_zero(O1); reg_zero(m);
  const uint32_t dst = c.sb + OFF_P + stsm_t_lane_off(c);
  reg_zero(l);
  attn1_step<true, false, false>(c, S0, S1, O0, O1, m, l, dst + 10240, 0, nt);
#pragma unroll 1
  for (int h = 0;; h += 2) {
    if ((h & 7) == 0) attn1_boundary(c, S0, l, m, h > 0, h < nt);
    if (h < nt) attn1_step<true, true, true>(c, S1, S0, O0, O1, m, l, dst, h + 1, nt);
    else attn1_step<false, true, false>(c, S1, S0, O0, O1, m, l, dst, h + 1, nt);
    if ((h & 7) == 0 && h) {
      attn1_store(c, O0, O1, (h >> 3) - 1);
      if (h == nt) break;
    }
    if (T_T == 0 && (h & 7) == 6 && h + 2 < nt) mbar_wait(c.bar + (B_QREADY + (((h + 2) >> 3) & 1)) * 8, ph ^ ((h + 2) >> 4));
    attn1_step<true, true, true>(c, S0, S1, O0, O1, m, l, dst + 10240, h + 2, nt);
  }
}

__device__ __forceinline__ void cluster_sync_relaxed() {
  asm volatile("barrier.cluster.arrive.relaxed.aligned;\nbarrier.cluster.wait.aligned;" ::: "memory");
}
__device__ __forceinline__ void store_rows(const CUtensorMap* m, uint32_t src, int c0, int row, int r0, int r1) {
#pragma unroll 1
  for (int r = r0; r < r1; r += 16) tma_store_2d(m, src + r * 128, c0, row + r);
  asm volatile("cp.async.bulk.commit_group;" ::: "memory");
  asm volatile("cp.async.bulk.wait_group.read 1;" ::: "memory");
}
__device__ __forceinline__ void store_drain() { asm volatile("cp.async.bulk.wait_group.read 0;" ::: "memory"); }
__device__ __forceinline__ void store_page(const CUtensorMap* m, uint32_t src, int c0, int row) {
  store_rows(m, src, c0, row, 0, 64);
  store_rows(m, src, c0, row, 64, SQ);
  store_drain();
}
__device__ __forceinline__ void set_flag(const unsigned* f, unsigned epoch) {
  asm volatile("fence.proxy.async.global;" ::: "memory");
  asm volatile("st.release.gpu.global.u32 [%0], %1;" ::"l"(f), "r"(epoch) : "memory");
}
__device__ __forceinline__ void wait_flag(const unsigned* f, unsigned epoch) {
  unsigned v;
  while (true) {
    asm volatile("ld.acquire.gpu.global.u32 %0, [%1];" : "=r"(v) : "l"(f) : "memory");
    if (v == epoch) break;
    __nanosleep(100);
  }
  asm volatile("fence.proxy.async.global;" ::: "memory");
}

__global__ void __cluster_dims__(2, 1, 1) __launch_bounds__(NTHREADS, 1) fused_kernel(const __grid_constant__ Maps maps) {
  extern __shared__ __align__(1024) uint8_t smem_raw[];
  const uint32_t sb = __shfl_sync(0xffffffffu, smem_u32(smem_raw), 0);
  if ((sb & 0x3FFFFu) != Ctx::s16 * 16) __trap();
  const uint32_t bar = sb + OFF_BAR;
  const int tid = threadIdx.x;
  const int wid = __shfl_sync(0xffffffffu, tid >> 5, 0);
  const int wg = wid >> 2, warp = wid & 3, lane = tid & 31;

  const int rank = blockIdx.x & 1, cl = blockIdx.x >> 1;
  const int vb = blockIdx.x;
  const int grp = cl & 7, idx = cl >> 3;
  const int br = grp >> 2, b = (grp & 3) * 2 + rank;
  const int ct = idx & 3, kh = idx >> 2;

  if (tid == 0) {
    for (int i = 0; i < 4; i++) {
      mbar_init(bar + (B_GFULL + i) * 8, 1);
      mbar_init(bar + (B_GEMPTY + i) * 8, 8);
      mbar_init(bar + (B_KVFULL + i) * 8, 1);
      mbar_init(bar + (B_KVEMPTY + i) * 8, 2);
      mbar_init(bar + (B_OSTG + i) * 8, 4);
    }
    mbar_init(bar + B_QFREEA * 8, 2);
    mbar_init(bar + B_QFREEB * 8, 2);
    mbar_init(bar + B_QFREEC * 8, 1);
    mbar_init(bar + B_PF * 8, 1);
    mbar_init(bar + B_PARK * 8, 1);
    mbar_init(bar + B_PE * 8, 4);
    mbar_init(bar + (B_PE + 1) * 8, 4);
    mbar_init(bar + (B_QREADY + 0) * 8, 1);
    mbar_init(bar + (B_QREADY + 1) * 8, 1);
    mbar_init(bar + B_DONE * 8, 4);
    sts_volatile(sb + OFF_PROG, 0);
    sts_volatile(sb + OFF_PROG + 4, 0);
    asm volatile("fence.mbarrier_init.release.cluster;" ::: "memory");
  } else if (tid == 256) {
    asm volatile("prefetch.tensormap [%0];" ::"l"(&maps.x[br]) : "memory");
    asm volatile("prefetch.tensormap [%0];" ::"l"(&maps.wq[br]) : "memory");
  }
  __syncthreads();
  cluster_sync_relaxed();

  if (wg < 2) {
    asm volatile("setmaxnreg.inc.sync.aligned.u32 240;");
    Ctx c;
    c.sb = sb; c.bar = bar; c.wg = __shfl_sync(0xffffffffu, tid >> 7, 1); c.warp = warp; c.lane = lane; c.lead = (warp | lane) == 0; c.smc = maps.smc; c.vb = vb;
    c.kg = maps.kp[br];
    c.vg = maps.vp[br];
    if (wg == 1) bar_arrive(1, 256);
#pragma unroll 1
    for (int gi = 0; gi < 2; gi++) {
      const int mode = (gi == 0 && kh) ? G_QPARK : G_QP;
      gemm_phase<false>(c, mode, 16, gi & 1, kh, 0);
      if (mode != G_QP) continue;
      if (kh) mbar_wait(bar + B_PARK * 8, 1);
      c.h0 = b * 32 + 2 * ct + (kh ? 8 : gi * 16);
      const int nt = gi == 1 && !kh ? 32 : 16;
      if (wg == T_N) attn_wg0(c, nt, gi & 1);
      else attn_wg1(c, nt, gi & 1);
    }
    gemm_phase<true>(c, G_OPF, kh ? 64 - NZS : NZS, 0, kh, g_epoch[blockIdx.x] + 1);
    if (__shfl_sync(0xffffffffu, tid_now(), 0) < 128) bar_sync(1, 256);
    if ((tid_now() & 127) == 0) mbar_arrive(bar + B_DONE * 8);
    __syncwarp();
    asm volatile("barrier.cluster.arrive.relaxed.aligned;\nbarrier.cluster.wait.aligned; // consumers" ::: "memory");
  } else {
    asm volatile("setmaxnreg.dec.sync.aligned.u32 24;");
    const bool el = lane == 0;
    const int orow = (br * 8 + b) * SQ;
    const unsigned* oflag = &g_oflag[(br * 8 + b) * 32 * 32];
    if (warp == 0) {
      uint64_t pol;
      asm volatile(POLSTR : "=l"(pol));
      const uint64_t kpol = pol;
      int g = 0;
#pragma unroll 1
      for (int gi = 0; gi < 2; gi++) {
        const int h0 = 2 * ct + (kh ? 24 - gi * 16 : gi * 16);
#pragma unroll 1
        for (int k = 0; k < 16; k++, g++) {
          const int s = g & 3;
          const uint32_t fb = bar + (B_GFULL + s) * 8;
          mbar_wait(bar + (B_GEMPTY + s) * 8, ((g >> 2) & 1) ^ 1);
          if (el) {
            mbar_expect_tx(fb, 51200);
            if (gi == 1 && !kh) tma_2d_hint(sb + g_x_off(s), &maps.x[br], k * 64, b * SQ, fb, pol); else
            tma_2d(sb + g_x_off(s), &maps.x[br], k * 64, b * SQ, fb);
            tma_3d_mc(sb + (rank ? g_w1_off(s) : g_w0_off(s)), &maps.wq[br], 0, k * 64, (h0 + rank) * 2, fb, 3, pol);
            sts_volatile(sb + OFF_PROG + 4, g + 1);
          }
        }
        if (gi == 0 && kh) continue;
        const int nt = gi == 1 && !kh ? 32 : 16;
#pragma unroll 1
        for (int p = 0; p < nt; p++) {
          if (p == 0) mbar_wait(bar + B_QFREEA * 8, gi & 1);
          else if (p == 2) mbar_wait(bar + B_QFREEB * 8, gi & 1);
          else if (p >= 4) mbar_wait(bar + (B_KVEMPTY + (p & 3)) * 8, ((p >> 2) - 1) & 1);
          if (p > 0 && p < 4) __nanosleep(KV_PACE);
          const uint32_t fb = bar + (B_KVFULL + (p & 3)) * 8;
          if (el) {
            mbar_expect_tx(fb, 32768);
            tma_3d_hint(sb + kv_off(2 * p), p == nt - 1 ? &maps.v[br] : &maps.k[br], 0, kv_row(b * 32 + h0, p == 0 ? 0 : p == nt - 1 ? p - 1 : p + 1), 0, fb, kpol);
            tma_3d_hint(sb + kv_off(2 * p + 1), p == 0 ? &maps.k[br] : &maps.v[br], 0, kv_row(b * 32 + h0, p == 0 ? 1 : p == nt - 1 ? p : p - 1), 0, fb, kpol);
          }
        }
      }
      const unsigned epoch = g_epoch[blockIdx.x] + 1;
#pragma unroll 1
      for (int k = kh ? 0 : 64 - NZS; k < (kh ? 64 - NZS : 64); k++, g++) {
        const int head = op_head(k >> 1);
        if ((k & 1) == 0 || g == 32) wait_flag(oflag + head * 32, epoch);
        const int s = g & 3;
        const uint32_t fb = bar + (B_GFULL + s) * 8;
        const int kc = head * 128 + (k & 1) * 64;
        mbar_wait(bar + (B_GEMPTY + s) * 8, ((g >> 2) & 1) ^ 1);
        if (el) {
          mbar_expect_tx(fb, 51200);
          tma_2d_hint(sb + g_x_off(s), &maps.o, kc, orow, fb, pol);
          tma_3d_mc(sb + (rank ? g_w1_off(s) : g_w0_off(s)), &maps.wo[br], 0, kc, ct * 4 + rank * 2, fb, 3, pol);
        }
      }
      if (el) mbar_arrive(bar + B_DONE * 8);
    } else if (warp == 1) {
      const unsigned epoch = g_epoch[blockIdx.x] + 1;
      if (kh) {
        const int qc = (24 + 2 * ct) * 128;
#pragma unroll 1
        for (int i = 0; i < 4; i++) {
          mbar_wait(bar + ((i & 1 ? B_QREADY : B_PE) + (i >> 1)) * 8, 0);
          if (el) store_page(&maps.os, sb + (i == 1 ? 0 : i == 2 ? OFF_Q + 3 * PAGE : OFF_P), qc + (i ^ 1) * 64, orow);
          __syncwarp();
          if (i == 1 || i == 2) {
            if (lane < 2) mbar_arrive_cluster(bar + (B_GEMPTY + 1 + i) * 8, lane, 4);
          } else if (el) {
            mbar_arrive(bar + B_PARK * 8);
          }
        }
        if (el) {
          asm volatile("cp.async.bulk.wait_group 0;" ::: "memory");
          set_flag(&g_aflag[(vb & 63) * 32], epoch);
        }
        __syncwarp();
      }
#pragma unroll 1
      for (int hd = 0; hd < (kh ? 2 : 6); hd++) {
        const int hh = hd & 1, pr = hd >> 1;
        const int head = 2 * ct + hh + (kh ? 8 : pr == 0 ? 0 : 8 + 8 * pr);
        const uint32_t q = sb + OFF_Q + hh * 2 * PAGE;
#pragma unroll 1
        for (int w = 0; w < 2; w++) {
          mbar_wait(bar + (B_OSTG + hh * 2 + w) * 8, pr & 1);
          if (el) {
            store_rows(&maps.os, q, head * 128, orow, w == T_T ? 64 : 0, w == T_T ? SQ : 64);
            store_rows(&maps.os, q + PAGE, head * 128 + 64, orow, w == T_T ? 64 : 0, w == T_T ? SQ : 64);
            if (w) store_drain();
          }
          __syncwarp();
        }
        if (pr == 1) {
          if (hh == 0) wait_flag(&g_aflag[(vb & 63) * 32], epoch);
          if (el) {
            const uint32_t qb = bar + (B_QREADY + hh) * 8;
            mbar_expect_tx(qb, 2 * PAGE);
            tma_2d(q, &maps.o, (head + 8) * 128, orow, qb);
            tma_2d(q + PAGE, &maps.o, (head + 8) * 128 + 64, orow, qb);
          }
        } else if (hh) {
          if (lane < 2) mbar_arrive_cluster(bar + (B_GEMPTY + 3) * 8, lane, 4);
        }
        if (el) {
          asm volatile("cp.async.bulk.wait_group 0;" ::: "memory");
          set_flag(oflag + head * 32, epoch);
        }
        __syncwarp();
        if (hh == 0 && pr != 1) {
          if (lane < 2) mbar_arrive_cluster(bar + B_GEMPTY * 8, lane, 2);
        }
      }
#pragma unroll 1
      for (int w = 0; w < 2; w++) {
        mbar_wait(bar + (B_QREADY + w) * 8, kh ^ 1);
        if (el) tma_store_2d(&maps.out, sb + OFF_Q + w * 2 * PAGE + PAGE, br * 1024 + ct * 256 + w * 128 + kh * 64, b * SQ);
      }
      if (el) {
        asm volatile("cp.async.bulk.commit_group;" ::: "memory");
        asm volatile("cp.async.bulk.wait_group.read 0;" ::: "memory");
        g_epoch[blockIdx.x] = epoch;
        mbar_arrive(bar + B_DONE * 8);
      }
    } else if (warp == 2) {
      const unsigned long long t0 = gtime();
      while (!mbar_try(bar + B_DONE * 8, 0)) {
        if (gtime() - t0 > 2000000000ull) __trap();
      }
    } else {
      const uint32_t pb = bar + B_PF * 8;
#pragma unroll 1
      for (int k = 0; k < 16; k++) {
        while (lds_volatile(sb + OFF_PROG + 4) + PF_LQ <= k + 16) __nanosleep(200);
        if (el) {
          asm volatile("mbarrier.expect_tx.relaxed.cta.shared::cta.b64 [%0], %1;" ::"r"(pb), "r"(1024) : "memory");
          tma_2d(sb + OFF_DUMMY, &maps.pwq[br], (2 * ct + (kh ? 8 : 16) + rank) * 128, k * 64, pb);
        }
      }
      if (el) mbar_arrive(pb);
      mbar_wait(pb, 0);
#pragma unroll 1
      for (int r = 0; r < (kh ? 1 : 2); r++) {
        if (r) {
          mbar_wait(bar + B_OSTG * 8, 1);
          mbar_wait(bar + (B_OSTG + 1) * 8, 1);
        }
        mbar_wait(bar + B_OSTG * 8, 0);
        mbar_wait(bar + (B_OSTG + 1) * 8, 0);
#pragma unroll 1
        for (int s = 0; s < 3; s++) {
          mbar_wait(bar + (B_KVEMPTY + (s ? s + 1 : 0)) * 8, 1);
          if (lane < 2) mbar_arrive_cluster(bar + (B_GEMPTY + s) * 8, lane, s ? 4 : 2);
        }
      }
    }
    __syncwarp();
    cluster_sync_relaxed();
  }
}

typedef CUresult (*EncodeFn)(CUtensorMap*, CUtensorMapDataType, cuuint32_t, void*, const cuuint64_t*, const cuuint64_t*, const cuuint32_t*, const cuuint32_t*,
                             CUtensorMapInterleave, CUtensorMapSwizzle, CUtensorMapL2promotion, CUtensorMapFloatOOBfill);

#define PROMO2 CU_TENSOR_MAP_L2_PROMOTION_L2_128B
#define PROMO3 CU_TENSOR_MAP_L2_PROMOTION_L2_128B
void enc2(EncodeFn fn, CUtensorMap* m, const void* p, uint64_t cols, uint64_t rows, uint32_t bc, uint32_t brows) {
  cuuint64_t dims[2] = {cols, rows};
  cuuint64_t str[1] = {cols * 2};
  cuuint32_t box[2] = {bc, brows};
  cuuint32_t es[2] = {1, 1};
  fn(m, CU_TENSOR_MAP_DATA_TYPE_BFLOAT16, 2, const_cast<void*>(p), dims, str, box, es, CU_TENSOR_MAP_INTERLEAVE_NONE, CU_TENSOR_MAP_SWIZZLE_128B,
     PROMO2, CU_TENSOR_MAP_FLOAT_OOB_FILL_NONE);
}
void encp(EncodeFn fn, CUtensorMap* m, const void* p, uint64_t cols, uint64_t rows, uint32_t brows) {
  cuuint64_t dims[2] = {cols, rows};
  cuuint64_t str[1] = {cols * 2};
  cuuint32_t box[2] = {8, brows};
  cuuint32_t es[2] = {1, 1};
  fn(m, CU_TENSOR_MAP_DATA_TYPE_BFLOAT16, 2, const_cast<void*>(p), dims, str, box, es, CU_TENSOR_MAP_INTERLEAVE_NONE, CU_TENSOR_MAP_SWIZZLE_NONE,
     CU_TENSOR_MAP_L2_PROMOTION_L2_256B, CU_TENSOR_MAP_FLOAT_OOB_FILL_NONE);
}
void enc3(EncodeFn fn, CUtensorMap* m, const void* p, uint64_t cols, uint64_t rows, uint32_t brows) {
  cuuint64_t dims[3] = {64, rows, cols / 64};
  cuuint64_t str[2] = {cols * 2, 128};
  cuuint32_t box[3] = {64, brows, 2};
  cuuint32_t es[3] = {1, 1, 1};
  fn(m, CU_TENSOR_MAP_DATA_TYPE_BFLOAT16, 3, const_cast<void*>(p), dims, str, box, es, CU_TENSOR_MAP_INTERLEAVE_NONE, CU_TENSOR_MAP_SWIZZLE_128B,
     PROMO3, CU_TENSOR_MAP_FLOAT_OOB_FILL_NONE);
}

}

extern "C" void kernel_launch(void* const* d_in, const int* in_sizes, int n_in, void* d_out, int out_size) {
  (void)in_sizes; (void)n_in; (void)out_size;
  void* fnp = nullptr;
  cudaDriverEntryPointQueryResult qres;
  cudaGetDriverEntryPoint("cuTensorMapEncodeTiled", &fnp, cudaEnableDefault, &qres);
  EncodeFn fn = (EncodeFn)fnp;
  void* optr = nullptr;
  cudaGetSymbolAddress(&optr, g_O);
  Maps maps;
  for (int br = 0; br < 2; br++) {
    enc2(fn, &maps.x[br], d_in[br * 5 + 0], 1024, 1152, 64, 144);
    enc3(fn, &maps.k[br], d_in[br * 5 + 1], 128, 131072, 64);
    enc3(fn, &maps.v[br], d_in[br * 5 + 2], 128, 131072, 64);
    enc3(fn, &maps.wq[br], d_in[br * 5 + 3], 4096, 1024, 64);
    enc3(fn, &maps.wo[br], d_in[br * 5 + 4], 1024, 4096, 64);
    maps.kp[br] = (const char*)d_in[br * 5 + 1];
    maps.vp[br] = (const char*)d_in[br * 5 + 2];
    encp(fn, &maps.pwq[br], d_in[br * 5 + 3], 4096, 1024, 64);
  }
  maps.smc = SM_C;
  enc2(fn, &maps.o, optr, 4096, 2304, 64, 144);
  enc2(fn, &maps.os, optr, 4096, 2304, 64, ST_ROWS);
  enc2(fn, &maps.out, d_out, 2048, 1152, 64, 144);
  cudaFuncSetAttribute(fused_kernel, cudaFuncAttributeMaxDynamicSharedMemorySize, SMEM_BYTES);
  fused_kernel<<<128, NTHREADS, SMEM_BYTES, cudaStreamPerThread>>>(maps);
}
```
